```python
import torch

def _softmax(x, axis=-1):
    return torch.softmax(x, dim=axis)
def _gelu(x):
    return torch.nn.functional.gelu(x, approximate="tanh")
def _silu(x):
    return torch.nn.functional.silu(x)
def _sigmoid(x):
    return torch.sigmoid(x)
def _layernorm(x, axis=-1, eps=1e-5):
    m = x.mean(dim=axis, keepdim=True)
    v = x.var(dim=axis, keepdim=True, unbiased=False)
    return (x - m) / torch.sqrt(v + eps)
def _scatter_add(tgt, idx, src, axis=0):
    return tgt.clone().index_add_(axis, idx, src)
def _segment_sum(src, seg, n):
    out = torch.zeros((n,) + src.shape[1:], dtype=src.dtype)
    return out.index_add_(0, seg, src)
def _pad(x, pw):
    flat = tuple(v for pair in reversed(pw) for v in pair)
    return torch.nn.functional.pad(x, flat)

kernel_name = 'gated_mix__linear_attn_block__ssm_conv_s4d__prompt'

def setup_inputs():

    _w = (lambda a: (lambda t: t.to(torch.bfloat16) if t.is_floating_point() else t)(torch.as_tensor(a)))
    def _A_setup():
        B, S, D = 1, 2048, 1024
        return {
            "x": _w((lambda *s: torch.randn(*s, dtype=torch.bfloat16) * 0.05)(B, S, D)),
            "wqkv": _w((lambda *s: torch.randn(*s, dtype=torch.bfloat16) * 0.8)(D, 3 * D)),
            "wo": _w((lambda *s: torch.randn(*s, dtype=torch.bfloat16) * 0.05)(D, D)),
        }
    _A_in = _A_setup()

    def _B_setup():
        Bsz, L, D, N = 1, 2048, 1024, 128
        return {
            "u": _w((lambda *s: torch.randn(*s, dtype=torch.bfloat16) * 0.05)(Bsz, L, D)),
            "log_A_real": _w((lambda *s: torch.randn(*s, dtype=torch.bfloat16) * 3.2)(D, N) * 0.5),
            "A_imag": _w((lambda *s: torch.randn(*s, dtype=torch.bfloat16) * 0.05)(D, N) * 3.14),
            "C_real": _w((lambda *s: torch.randn(*s, dtype=torch.bfloat16) * 0.8)(D, N) / N ** 0.5),
            "C_imag": _w((lambda *s: torch.randn(*s, dtype=torch.bfloat16) * 0.8)(D, N) / N ** 0.5),
            "log_dt": _w((lambda *s: torch.randn(*s, dtype=torch.bfloat16) * 0.05)(D) * 0.5 - 4.0),
            "D_skip": _w((lambda *s: torch.randn(*s, dtype=torch.bfloat16) * 0.1)(D)),
        }
    _B_in = _B_setup()

    return {
        "A_x": _A_in["x"],
        "A_wqkv": _A_in["wqkv"],
        "A_wo": _A_in["wo"],
        "B_u": _B_in["u"],
        "B_log_A_real": _B_in["log_A_real"],
        "B_A_imag": _B_in["A_imag"],
        "B_C_real": _B_in["C_real"],
        "B_C_imag": _B_in["C_imag"],
        "B_log_dt": _B_in["log_dt"],
        "B_D_skip": _B_in["D_skip"],
        "gate_w": _w((lambda *s: torch.randn(*s, dtype=torch.bfloat16) * 0.05)(1024) * 16.0),
    }

def reference(A_x, A_wqkv, A_wo, B_u, B_log_A_real, B_A_imag, B_C_real, B_C_imag, B_log_dt, B_D_skip, gate_w):
    def _A_ref(x, wqkv, wo):
        B, S, D = x.shape
        H = 32; Dh = D // H
        qkv = (lambda x, *d: x.permute(*d))((x @ wqkv).reshape(B, S, 3, H, Dh), 2, 0, 3, 1, 4)
        q, k, v = qkv[0], qkv[1], qkv[2]
        phi = lambda t: torch.where(t > 0, t + 1, torch.exp(t)) + 1e-6
        pq, pk = phi(q), phi(k)
        kv = torch.einsum("bhsd,bhse->bhde", pk, v)
        z = torch.einsum("bhsd->bhd", pk)
        num = torch.einsum("bhqd,bhde->bhqe", pq, kv)
        den = torch.einsum("bhqd,bhd->bhq", pq, z)[..., None] + 1e-6
        o = num / den
        return (lambda x, *d: x.permute(*d))(o, 0, 2, 1, 3).reshape(B, S, D) @ wo

    def _B_ref(u, log_A_real, A_imag, C_real, C_imag, log_dt, D_skip):
        L = u.shape[1]
        dt = torch.exp(log_dt)
        A = -torch.exp(log_A_real) + 1j * A_imag
        C = (C_real + 1j * C_imag) * dt[:, None]
        pos = (lambda x, dt: x.to(dt))(torch.arange(L), log_dt.dtype)
        P = torch.exp((A * dt[:, None])[:, :, None] * pos[None, None, :])
        K = 2.0 * torch.einsum("dn,dnl->dl", C, P).real
        L2 = 2 * L
        u_t = (lambda x, *d: x.permute(*d))(u, 0, 2, 1)
        Kf = (lambda x, *a, **k: torch.fft.rfft(x.float(), *a, **k))(K, L2)
        Uf = (lambda x, *a, **k: torch.fft.rfft(x.float(), *a, **k))(u_t, L2)
        y = (lambda x, *a, **k: torch.fft.irfft(x, *a, **k).to(torch.bfloat16))(Uf * Kf[None, :, :], L2)[:, :, :L]
        y = (lambda x, *d: x.permute(*d))(y, 0, 2, 1)
        return y + u * D_skip[None, None, :]

    x = A_x
    g = _sigmoid((x * gate_w).sum(-1, keepdims=True))
    a = _A_ref(x, A_wqkv, A_wo)
    b = _B_ref(x, B_log_A_real, B_A_imag, B_C_real, B_C_imag, B_log_dt, B_D_skip)
    return g * a + (1 - g) * b
```

```cpp
#include <cuda_runtime.h>
#include <cuda_bf16.h>
#include <cuda.h>
#include <stdint.h>

namespace {

constexpr int SEQ = 2048;
constexpr int DM  = 1024;
constexpr int NST = 128;

__device__ __nv_bfloat16 g_o[SEQ * DM];
__device__ __nv_bfloat16 g_b[SEQ * DM];
__device__ float         g_gate[SEQ];
__device__ float         g_part[16 * 8 * 64 * 36];
__device__ unsigned int  g_cnt[16];

#define TSTAMP(k, i)
#define TSTAMPW(k, i, cond)
#define GSTAMP(k, i, cond)
__device__ __forceinline__ uint32_t smem_u32(const void* p) { return (uint32_t)__cvta_generic_to_shared(p); }
__device__ __forceinline__ float bf16r(float x) { return __bfloat162float(__float2bfloat16_rn(x)); }
__device__ __forceinline__ uint32_t pack_bf16(float lo, float hi) {
  __nv_bfloat162 v = __floats2bfloat162_rn(lo, hi);
  return *reinterpret_cast<uint32_t*>(&v);
}
__device__ __forceinline__ void mbar_init(uint32_t bar, uint32_t cnt) {
  asm volatile("mbarrier.init.shared::cta.b64 [%0], %1;" ::"r"(bar), "r"(cnt));
}
__device__ __forceinline__ void mbar_expect_tx(uint32_t bar, uint32_t bytes) {
  asm volatile("mbarrier.arrive.expect_tx.shared::cta.b64 _, [%0], %1;" ::"r"(bar), "r"(bytes) : "memory");
}
__device__ __forceinline__ void mbar_arrive(uint32_t bar) {
  asm volatile("mbarrier.arrive.shared::cta.b64 _, [%0];" ::"r"(bar) : "memory");
}
__device__ __forceinline__ void mbar_wait(uint32_t bar, uint32_t parity) {
  asm volatile(
      "{\n.reg .pred p;\n"
      "WAIT_LOOP:\n"
      "mbarrier.try_wait.parity.shared::cta.b64 p, [%0], %1;\n"
      "@p bra WAIT_DONE;\n"
      "bra WAIT_LOOP;\n"
      "WAIT_DONE:\n}\n" ::"r"(bar), "r"(parity) : "memory");
}
__device__ __forceinline__ void tma_load_2d(uint32_t dst, const CUtensorMap* tm, uint32_t bar, int c0, int c1) {
  asm volatile(
      "cp.async.bulk.tensor.2d.shared::cluster.global.mbarrier::complete_tx::bytes [%0], [%1, {%3, %4}], [%2];"
      ::"r"(dst), "l"(tm), "r"(bar), "r"(c0), "r"(c1) : "memory");
}
__device__ __forceinline__ void tma_store_2d(const CUtensorMap* tm, uint32_t src, int c0, int c1) {
  asm volatile("cp.async.bulk.tensor.2d.global.shared::cta.bulk_group [%0, {%2, %3}], [%1];"
               ::"l"(tm), "r"(src), "r"(c0), "r"(c1) : "memory");
}
__device__ __forceinline__ void bulk_commit() { asm volatile("cp.async.bulk.commit_group;" ::: "memory"); }
__device__ __forceinline__ void fence_proxy_async() { asm volatile("fence.proxy.async.shared::cta;" ::: "memory"); }
__device__ __forceinline__ void named_bar(int id, int n) { asm volatile("bar.sync %0, %1;" ::"r"(id), "r"(n) : "memory"); }
__device__ __forceinline__ void wgmma_fence() { asm volatile("wgmma.fence.sync.aligned;" ::: "memory"); }
__device__ __forceinline__ void wgmma_commit() { asm volatile("wgmma.commit_group.sync.aligned;" ::: "memory"); }
template <int N> __device__ __forceinline__ void wgmma_wait() { asm volatile("wgmma.wait_group.sync.aligned %0;" ::"n"(N) : "memory"); }
template <int R> __device__ __forceinline__ void reg_alloc() { asm volatile("setmaxnreg.inc.sync.aligned.u32 %0;" ::"n"(R)); }
template <int R> __device__ __forceinline__ void reg_dealloc() { asm volatile("setmaxnreg.dec.sync.aligned.u32 %0;" ::"n"(R)); }

__device__ __forceinline__ uint64_t make_desc(uint32_t addr, uint32_t lbo, uint32_t sbo, uint32_t swz) {
  return (uint64_t)((addr & 0x3FFFF) >> 4) | ((uint64_t)(lbo >> 4) << 16) | ((uint64_t)(sbo >> 4) << 32) |
         ((uint64_t)swz << 62);
}

__device__ __forceinline__ void wgmma_n192_ss_tb(float* d, uint64_t descA, uint64_t descB, int scaleD) {
  asm volatile("{\n.reg .pred p;\nsetp.ne.b32 p, %98, 0;\nwgmma.mma_async.sync.aligned.m64n192k16.f32.bf16.bf16 {%0, %1, %2, %3, %4, %5, %6, %7, %8, %9, %10, %11, %12, %13, %14, %15, %16, %17, %18, %19, %20, %21, %22, %23, %24, %25, %26, %27, %28, %29, %30, %31, %32, %33, %34, %35, %36, %37, %38, %39, %40, %41, %42, %43, %44, %45, %46, %47, %48, %49, %50, %51, %52, %53, %54, %55, %56, %57, %58, %59, %60, %61, %62, %63, %64, %65, %66, %67, %68, %69, %70, %71, %72, %73, %74, %75, %76, %77, %78, %79, %80, %81, %82, %83, %84, %85, %86, %87, %88, %89, %90, %91, %92, %93, %94, %95}, %96, %97, p, 1, 1, 0, 1;\n}\n"
    : "+f"(d[0]), "+f"(d[1]), "+f"(d[2]), "+f"(d[3]), "+f"(d[4]), "+f"(d[5]), "+f"(d[6]), "+f"(d[7]), "+f"(d[8]), "+f"(d[9]), "+f"(d[10]), "+f"(d[11]), "+f"(d[12]), "+f"(d[13]), "+f"(d[14]), "+f"(d[15]), "+f"(d[16]), "+f"(d[17]), "+f"(d[18]), "+f"(d[19]), "+f"(d[20]), "+f"(d[21]), "+f"(d[22]), "+f"(d[23]), "+f"(d[24]), "+f"(d[25]), "+f"(d[26]), "+f"(d[27]), "+f"(d[28]), "+f"(d[29]), "+f"(d[30]), "+f"(d[31]), "+f"(d[32]), "+f"(d[33]), "+f"(d[34]), "+f"(d[35]), "+f"(d[36]), "+f"(d[37]), "+f"(d[38]), "+f"(d[39]), "+f"(d[40]), "+f"(d[41]), "+f"(d[42]), "+f"(d[43]), "+f"(d[44]), "+f"(d[45]), "+f"(d[46]), "+f"(d[47]), "+f"(d[48]), "+f"(d[49]), "+f"(d[50]), "+f"(d[51]), "+f"(d[52]), "+f"(d[53]), "+f"(d[54]), "+f"(d[55]), "+f"(d[56]), "+f"(d[57]), "+f"(d[58]), "+f"(d[59]), "+f"(d[60]), "+f"(d[61]), "+f"(d[62]), "+f"(d[63]), "+f"(d[64]), "+f"(d[65]), "+f"(d[66]), "+f"(d[67]), "+f"(d[68]), "+f"(d[69]), "+f"(d[70]), "+f"(d[71]), "+f"(d[72]), "+f"(d[73]), "+f"(d[74]), "+f"(d[75]), "+f"(d[76]), "+f"(d[77]), "+f"(d[78]), "+f"(d[79]), "+f"(d[80]), "+f"(d[81]), "+f"(d[82]), "+f"(d[83]), "+f"(d[84]), "+f"(d[85]), "+f"(d[86]), "+f"(d[87]), "+f"(d[88]), "+f"(d[89]), "+f"(d[90]), "+f"(d[91]), "+f"(d[92]), "+f"(d[93]), "+f"(d[94]), "+f"(d[95])
    : "l"(descA), "l"(descB), "r"(scaleD));
}

__device__ __forceinline__ void wgmma_n128_ss_tb(float* d, uint64_t descA, uint64_t descB, int scaleD) {
  asm volatile("{\n.reg .pred p;\nsetp.ne.b32 p, %66, 0;\nwgmma.mma_async.sync.aligned.m64n128k16.f32.bf16.bf16 {%0, %1, %2, %3, %4, %5, %6, %7, %8, %9, %10, %11, %12, %13, %14, %15, %16, %17, %18, %19, %20, %21, %22, %23, %24, %25, %26, %27, %28, %29, %30, %31, %32, %33, %34, %35, %36, %37, %38, %39, %40, %41, %42, %43, %44, %45, %46, %47, %48, %49, %50, %51, %52, %53, %54, %55, %56, %57, %58, %59, %60, %61, %62, %63}, %64, %65, p, 1, 1, 0, 1;\n}\n"
    : "+f"(d[0]), "+f"(d[1]), "+f"(d[2]), "+f"(d[3]), "+f"(d[4]), "+f"(d[5]), "+f"(d[6]), "+f"(d[7]), "+f"(d[8]), "+f"(d[9]), "+f"(d[10]), "+f"(d[11]), "+f"(d[12]), "+f"(d[13]), "+f"(d[14]), "+f"(d[15]), "+f"(d[16]), "+f"(d[17]), "+f"(d[18]), "+f"(d[19]), "+f"(d[20]), "+f"(d[21]), "+f"(d[22]), "+f"(d[23]), "+f"(d[24]), "+f"(d[25]), "+f"(d[26]), "+f"(d[27]), "+f"(d[28]), "+f"(d[29]), "+f"(d[30]), "+f"(d[31]), "+f"(d[32]), "+f"(d[33]), "+f"(d[34]), "+f"(d[35]), "+f"(d[36]), "+f"(d[37]), "+f"(d[38]), "+f"(d[39]), "+f"(d[40]), "+f"(d[41]), "+f"(d[42]), "+f"(d[43]), "+f"(d[44]), "+f"(d[45]), "+f"(d[46]), "+f"(d[47]), "+f"(d[48]), "+f"(d[49]), "+f"(d[50]), "+f"(d[51]), "+f"(d[52]), "+f"(d[53]), "+f"(d[54]), "+f"(d[55]), "+f"(d[56]), "+f"(d[57]), "+f"(d[58]), "+f"(d[59]), "+f"(d[60]), "+f"(d[61]), "+f"(d[62]), "+f"(d[63])
    : "l"(descA), "l"(descB), "r"(scaleD));
}

__device__ __forceinline__ void wgmma_n64_ss_tatb(float* d, uint64_t descA, uint64_t descB, int scaleD) {
  asm volatile("{\n.reg .pred p;\nsetp.ne.b32 p, %34, 0;\nwgmma.mma_async.sync.aligned.m64n64k16.f32.bf16.bf16 {%0, %1, %2, %3, %4, %5, %6, %7, %8, %9, %10, %11, %12, %13, %14, %15, %16, %17, %18, %19, %20, %21, %22, %23, %24, %25, %26, %27, %28, %29, %30, %31}, %32, %33, p, 1, 1, 1, 1;\n}\n"
    : "+f"(d[0]), "+f"(d[1]), "+f"(d[2]), "+f"(d[3]), "+f"(d[4]), "+f"(d[5]), "+f"(d[6]), "+f"(d[7]), "+f"(d[8]), "+f"(d[9]), "+f"(d[10]), "+f"(d[11]), "+f"(d[12]), "+f"(d[13]), "+f"(d[14]), "+f"(d[15]), "+f"(d[16]), "+f"(d[17]), "+f"(d[18]), "+f"(d[19]), "+f"(d[20]), "+f"(d[21]), "+f"(d[22]), "+f"(d[23]), "+f"(d[24]), "+f"(d[25]), "+f"(d[26]), "+f"(d[27]), "+f"(d[28]), "+f"(d[29]), "+f"(d[30]), "+f"(d[31])
    : "l"(descA), "l"(descB), "r"(scaleD));
}

__device__ __forceinline__ void wgmma_n8_ss_ta(float* d, uint64_t descA, uint64_t descB, int scaleD) {
  asm volatile("{\n.reg .pred p;\nsetp.ne.b32 p, %6, 0;\nwgmma.mma_async.sync.aligned.m64n8k16.f32.bf16.bf16 {%0, %1, %2, %3}, %4, %5, p, 1, 1, 1, 0;\n}\n"
    : "+f"(d[0]), "+f"(d[1]), "+f"(d[2]), "+f"(d[3])
    : "l"(descA), "l"(descB), "r"(scaleD));
}

__device__ __forceinline__ void wgmma_n72_rs(float* d, uint32_t a0, uint32_t a1, uint32_t a2, uint32_t a3, uint64_t descB, int scaleD) {
  asm volatile("{\n.reg .pred p;\nsetp.ne.b32 p, %41, 0;\nwgmma.mma_async.sync.aligned.m64n72k16.f32.bf16.bf16 {%0, %1, %2, %3, %4, %5, %6, %7, %8, %9, %10, %11, %12, %13, %14, %15, %16, %17, %18, %19, %20, %21, %22, %23, %24, %25, %26, %27, %28, %29, %30, %31, %32, %33, %34, %35}, {%36, %37, %38, %39}, %40, p, 1, 1, 0;\n}\n"
    : "+f"(d[0]), "+f"(d[1]), "+f"(d[2]), "+f"(d[3]), "+f"(d[4]), "+f"(d[5]), "+f"(d[6]), "+f"(d[7]), "+f"(d[8]), "+f"(d[9]), "+f"(d[10]), "+f"(d[11]), "+f"(d[12]), "+f"(d[13]), "+f"(d[14]), "+f"(d[15]), "+f"(d[16]), "+f"(d[17]), "+f"(d[18]), "+f"(d[19]), "+f"(d[20]), "+f"(d[21]), "+f"(d[22]), "+f"(d[23]), "+f"(d[24]), "+f"(d[25]), "+f"(d[26]), "+f"(d[27]), "+f"(d[28]), "+f"(d[29]), "+f"(d[30]), "+f"(d[31]), "+f"(d[32]), "+f"(d[33]), "+f"(d[34]), "+f"(d[35])
    : "r"(a0), "r"(a1), "r"(a2), "r"(a3), "l"(descB), "r"(scaleD));
}

__device__ __forceinline__ void wgmma_n32_rs(float* d, uint32_t a0, uint32_t a1, uint32_t a2, uint32_t a3, uint64_t descB, int scaleD) {
  asm volatile("{\n.reg .pred p;\nsetp.ne.b32 p, %21, 0;\nwgmma.mma_async.sync.aligned.m64n32k16.f32.bf16.bf16 {%0, %1, %2, %3, %4, %5, %6, %7, %8, %9, %10, %11, %12, %13, %14, %15}, {%16, %17, %18, %19}, %20, p, 1, 1, 0;\n}\n"
    : "+f"(d[0]), "+f"(d[1]), "+f"(d[2]), "+f"(d[3]), "+f"(d[4]), "+f"(d[5]), "+f"(d[6]), "+f"(d[7]), "+f"(d[8]), "+f"(d[9]), "+f"(d[10]), "+f"(d[11]), "+f"(d[12]), "+f"(d[13]), "+f"(d[14]), "+f"(d[15])
    : "r"(a0), "r"(a1), "r"(a2), "r"(a3), "l"(descB), "r"(scaleD));
}

__device__ __forceinline__ float ex2f(float x) { float r; asm("ex2.approx.ftz.f32 %0, %1;" : "=f"(r) : "f"(x)); return r; }
__device__ __forceinline__ float lo_f(uint32_t p) { return __uint_as_float(p << 16); }
__device__ __forceinline__ float hi_f(uint32_t p) { return __uint_as_float(p & 0xffff0000u); }
__device__ __forceinline__ uint32_t phi2(float t0, float t1) {
  const uint32_t p = pack_bf16(t0, t1);
  const float b0 = lo_f(p), b1 = hi_f(p);
  const float e0 = ex2f(b0 * 1.4426950408889634f), e1 = ex2f(b1 * 1.4426950408889634f);
  const float r0 = b0 > 0.f ? b0 + 1.f : e0, r1 = b1 > 0.f ? b1 + 1.f : e1;
  const uint32_t q = pack_bf16(r0, r1);
  return pack_bf16(lo_f(q) + 1e-6f, hi_f(q) + 1e-6f);
}
__device__ __forceinline__ void sts32(uint32_t addr, uint32_t v) { asm volatile("st.shared.b32 [%0], %1;" ::"r"(addr), "r"(v) : "memory"); }
__device__ __forceinline__ uint32_t lds32(uint32_t addr) { uint32_t v; asm volatile("ld.shared.b32 %0, [%1];" : "=r"(v) : "r"(addr) : "memory"); return v; }
__device__ __forceinline__ void bulk_wait0_read() { asm volatile("cp.async.bulk.wait_group.read 0;" ::: "memory"); }

__device__ __forceinline__ void cexp_fast(float a2, float br, float p, float& re, float& im) {
  const float m = ex2f(a2 * p);
  float r = br * p;
  r = r - rintf(r);
  r *= 6.283185307179586f;
  re = m * __cosf(r);
  im = m * __sinf(r);
}
__device__ __forceinline__ void cmul(float ar, float ai, float br, float bi, float& re, float& im) {
  re = ar * br - ai * bi;
  im = ar * bi + ai * br;
}
__device__ __forceinline__ uint32_t pack_h2(float lo, float hi) {
  uint32_t r;
  asm("cvt.rn.f16x2.f32 %0, %1, %2;" : "=r"(r) : "f"(hi), "f"(lo));
  return r;
}
__device__ __forceinline__ void mma_f16(float* d, uint32_t a0, uint32_t a1, uint32_t a2, uint32_t a3, uint32_t b0, uint32_t b1) {
  asm volatile("mma.sync.aligned.m16n8k16.row.col.f32.f16.f16.f32 {%0,%1,%2,%3}, {%4,%5,%6,%7}, {%8,%9}, {%0,%1,%2,%3};"
               : "+f"(d[0]), "+f"(d[1]), "+f"(d[2]), "+f"(d[3]) : "r"(a0), "r"(a1), "r"(a2), "r"(a3), "r"(b0), "r"(b1));
}
__device__ __forceinline__ void mma_bf16(float* d, uint32_t a0, uint32_t a1, uint32_t a2, uint32_t a3, uint32_t b0, uint32_t b1) {
  asm volatile("mma.sync.aligned.m16n8k16.row.col.f32.bf16.bf16.f32 {%0,%1,%2,%3}, {%4,%5,%6,%7}, {%8,%9}, {%0,%1,%2,%3};"
               : "+f"(d[0]), "+f"(d[1]), "+f"(d[2]), "+f"(d[3]) : "r"(a0), "r"(a1), "r"(a2), "r"(a3), "r"(b0), "r"(b1));
}
__device__ __forceinline__ void ldsm_x4(uint32_t addr, uint32_t& r0, uint32_t& r1, uint32_t& r2, uint32_t& r3) {
  asm volatile("ldmatrix.sync.aligned.m8n8.x4.shared.b16 {%0,%1,%2,%3}, [%4];"
               : "=r"(r0), "=r"(r1), "=r"(r2), "=r"(r3) : "r"(addr));
}
__device__ __forceinline__ void ldsm_x4_t(uint32_t addr, uint32_t& r0, uint32_t& r1, uint32_t& r2, uint32_t& r3) {
  asm volatile("ldmatrix.sync.aligned.m8n8.x4.trans.shared.b16 {%0,%1,%2,%3}, [%4];"
               : "=r"(r0), "=r"(r1), "=r"(r2), "=r"(r3) : "r"(addr));
}
__device__ __forceinline__ void ldsm_x2(uint32_t addr, uint32_t& r0, uint32_t& r1) {
  asm volatile("ldmatrix.sync.aligned.m8n8.x2.shared.b16 {%0,%1}, [%2];" : "=r"(r0), "=r"(r1) : "r"(addr));
}
__device__ __forceinline__ uint4 lds128(uint32_t addr) {
  uint4 v;
  asm volatile("ld.shared.v4.b32 {%0,%1,%2,%3}, [%4];" : "=r"(v.x), "=r"(v.y), "=r"(v.z), "=r"(v.w) : "r"(addr));
  return v;
}
__device__ __forceinline__ void sts128(uint32_t addr, uint32_t a, uint32_t b, uint32_t c, uint32_t d) {
  asm volatile("st.shared.v4.b32 [%0], {%1,%2,%3,%4};" ::"r"(addr), "r"(a), "r"(b), "r"(c), "r"(d) : "memory");
}

__device__ __forceinline__ void kgen_half(uint32_t tab, int lane, const float (&par)[2][4], float (&ka)[5][4], float& klast) {
  const uint32_t lo_t = tab, h_t = tab + 16 * 144;
#pragma unroll
  for (int qq = 0; qq < 2; ++qq) {
    const float a2 = par[qq][0], br = par[qq][1], cr = par[qq][2], ci = par[qq][3];
    float e1r, e1i, e8r, e8i, eBr, eBi;
    cexp_fast(a2, br, 1.f, e1r, e1i);
    cexp_fast(a2, br, 8.f, e8r, e8i);
    cexp_fast(a2, br, 128.f, eBr, eBi);
    float e2r, e2i, e4r, e4i;
    cmul(e1r, e1i, e1r, e1i, e2r, e2i);
    cmul(e2r, e2i, e2r, e2i, e4r, e4i);
    float lr = 1.f, li = 0.f;
    float vr = 1.f, vi = 0.f;
#pragma unroll
    for (int st = 0; st < 16; ++st) {
      sts32(lo_t + st * 144 + lane * 4, pack_h2(lr, li));
      { float nr, ni; cmul(lr, li, e8r, -e8i, nr, ni); lr = nr; li = ni; }
      const int ph = st;
      float hr, hi_;
      if (ph == 0) { hr = cr; hi_ = ci; } else cmul(cr, ci, vr, vi, hr, hi_);
      const int n = ph < 2 ? 8 : (ph < 4 ? 4 : (ph < 8 ? 2 : 1));
      const int row0 = ph < 2 ? 8 * ph : (ph < 4 ? 16 + (ph - 2) * 4 : (ph < 8 ? 24 + (ph - 4) * 2 : 32 + ph - 8));
#pragma unroll
      for (int o = 0; o < n; ++o) {
        sts32(h_t + (row0 + o) * 144 + lane * 4, pack_h2(hr, hi_));
        if (o + 1 < n) {
          float nr, ni;
          if (ph < 2) cmul(hr, hi_, e1r, e1i, nr, ni);
          else if (ph < 4) cmul(hr, hi_, e2r, e2i, nr, ni);
          else cmul(hr, hi_, e4r, e4i, nr, ni);
          hr = nr; hi_ = ni;
        }
      }
      { float nr, ni; cmul(vr, vi, eBr, eBi, nr, ni); vr = nr; vi = ni; }
    }
    klast += cr * vr - ci * vi;
    __syncwarp();
#pragma unroll
    for (int ks = 0; ks < 4; ++ks) {
      uint32_t a0, a1, a2_, a3;
      ldsm_x4(lo_t + (uint32_t)((lane & 15) * 144 + ks * 32 + (lane >> 4) * 16), a0, a1, a2_, a3);
      uint32_t b[5][2];
      ldsm_x4(h_t + (uint32_t)(((lane & 7) + (lane >> 4) * 8) * 144 + ks * 32 + ((lane >> 3) & 1) * 16), b[0][0], b[0][1], b[1][0], b[1][1]);
      ldsm_x4(h_t + (uint32_t)((16 + (lane & 7) + (lane >> 4) * 8) * 144 + ks * 32 + ((lane >> 3) & 1) * 16), b[2][0], b[2][1], b[3][0], b[3][1]);
      ldsm_x2(h_t + (uint32_t)((32 + (lane & 7)) * 144 + ks * 32 + ((lane >> 3) & 1) * 16), b[4][0], b[4][1]);
#pragma unroll
      for (int t = 0; t < 5; ++t) mma_f16(ka[t], a0, a1, a2_, a3, b[t][0], b[t][1]);
    }
    __syncwarp();
  }
}
__device__ __forceinline__ void gate_row(int row, int lane, const __nv_bfloat16* __restrict__ x, const __nv_bfloat16* __restrict__ gw) {
  const uint4* xr = reinterpret_cast<const uint4*>(x + (size_t)row * DM);
  const uint4* wr = reinterpret_cast<const uint4*>(gw);
  float sum = 0.f;
#pragma unroll
  for (int i = 0; i < 4; ++i) {
    const uint4 a = __ldg(xr + lane + 32 * i), w = __ldg(wr + lane + 32 * i);
    const uint32_t aw[4] = {a.x, a.y, a.z, a.w}, ww[4] = {w.x, w.y, w.z, w.w};
#pragma unroll
    for (int j = 0; j < 4; ++j) {
      const uint32_t p = pack_bf16(lo_f(aw[j]) * lo_f(ww[j]), hi_f(aw[j]) * hi_f(ww[j]));
      sum += lo_f(p) + hi_f(p);
    }
  }
#pragma unroll
  for (int o = 16; o; o >>= 1) sum += __shfl_xor_sync(0xffffffffu, sum, o);
  if (lane == 0) {
    const float sb = bf16r(sum);
    g_gate[row] = bf16r(1.f / (1.f + __expf(-sb)));
  }
}

constexpr int K1_STAGES = 4;
constexpr int K1_PROD_REGS = 40, K1_CONS_REGS = 232;
constexpr int K1_A_BYTES = 256 * 128;
constexpr int K1_B_BYTES = 192 * 128;
constexpr int K1_STAGE_BYTES = K1_A_BYTES + K1_B_BYTES;
constexpr int K1_OFF_BAR = K1_STAGES * K1_STAGE_BYTES;
constexpr int K1_OFF_TAB = K1_OFF_BAR + 128;
constexpr int K1_SMEM = K1_OFF_TAB + 1024;
constexpr int E_PK = 0;
constexpr int E_V = 32768;
constexpr int E_ONES = 65536;
constexpr int E_XCH = 66560;
constexpr int E_KVB = 81920;
constexpr int E_O = 98304;

__global__ void __launch_bounds__(384, 1)
k1_qkv_attn(const __grid_constant__ CUtensorMap tm_x, const __grid_constant__ CUtensorMap tm_w,
            const __grid_constant__ CUtensorMap tm_o, const __nv_bfloat16* __restrict__ x,
            const __nv_bfloat16* __restrict__ lar, const __nv_bfloat16* __restrict__ aim,
            const __nv_bfloat16* __restrict__ cre, const __nv_bfloat16* __restrict__ cim,
            const __nv_bfloat16* __restrict__ wo, const __nv_bfloat16* __restrict__ gw) {
  extern __shared__ uint8_t smem_raw[];
  const uint32_t sbase = (smem_u32(smem_raw) + 1023u) & ~1023u;
  uint8_t* sptr = smem_raw + (sbase - smem_u32(smem_raw));
  const uint32_t bar_full = sbase + K1_OFF_BAR;
  const uint32_t bar_empty = bar_full + 8 * K1_STAGES;
  const int tid = threadIdx.x;
  const int wg = tid >> 7;
  const int mb = blockIdx.x & 7;
  const int hp = blockIdx.x >> 3;
  if (tid == 0) {
    asm volatile("prefetch.tensormap [%0];" ::"l"(&tm_x) : "memory");
    asm volatile("prefetch.tensormap [%0];" ::"l"(&tm_w) : "memory");
    asm volatile("prefetch.tensormap [%0];" ::"l"(&tm_o) : "memory");
    for (int s = 0; s < K1_STAGES; ++s) {
      mbar_init(bar_full + 8 * s, 1);
      mbar_init(bar_empty + 8 * s, 2);
    }
    asm volatile("fence.mbarrier_init.release.cluster;" ::: "memory");
  }
  __syncthreads();

  asm volatile("griddepcontrol.launch_dependents;");
  TSTAMPW(0, 0, tid == 128);
  GSTAMP(0, 14, tid == 128);
  if (wg == 0) {
    reg_dealloc<K1_PROD_REGS>();
    if (tid >= 32) {
      const int w = (tid >> 5) - 1, lane = tid & 31;
      {
        const char* pw = reinterpret_cast<const char*>(wo) + (size_t)blockIdx.x * 16384;
        for (int i = (tid - 32) * 128; i < 16384; i += 96 * 128) asm volatile("prefetch.global.L2 [%0];" ::"l"(pw + i));
        const char* pp[4] = {(const char*)lar, (const char*)aim, (const char*)cre, (const char*)cim};
        if (tid - 32 < 64) {
          const int a = (tid - 32) >> 4, l = (tid - 32) & 15;
          asm volatile("prefetch.global.L2 [%0];" ::"l"(pp[a] + (size_t)blockIdx.x * 2048 + l * 128));
        }
      }
      for (int r = w; r < 16; r += 3) gate_row(mb * 256 + hp * 16 + r, lane, x, gw);
      TSTAMPW(0, 10, tid == 32);
    } else if (tid == 0) {
      for (int kt = 0; kt < 16; ++kt) {
        const int s = kt % K1_STAGES;
        const uint32_t ph = (kt / K1_STAGES) & 1;
        mbar_wait(bar_empty + 8 * s, ph ^ 1);
        mbar_expect_tx(bar_full + 8 * s, K1_STAGE_BYTES);
        const uint32_t sa = sbase + s * K1_STAGE_BYTES;
        const uint32_t sb = sa + K1_A_BYTES;
        tma_load_2d(sa, &tm_x, bar_full + 8 * s, kt * 64, mb * 256);
        tma_load_2d(sb, &tm_w, bar_full + 8 * s, hp * 64, kt * 64);
        tma_load_2d(sb + 8192, &tm_w, bar_full + 8 * s, 1024 + hp * 64, kt * 64);
        tma_load_2d(sb + 16384, &tm_w, bar_full + 8 * s, 2048 + hp * 64, kt * 64);
      }
    }
  } else {
    reg_alloc<K1_CONS_REGS>();
    const int cw = wg - 1;
    const int lt = tid & 127;
    const int warp = lt >> 5, lane = lt & 31, g = lane >> 2, c = lane & 3;
    float acc[2][96];
#pragma unroll
    for (int i = 0; i < 96; ++i) { acc[0][i] = 0.f; acc[1][i] = 0.f; }

    for (int kt = 0; kt < 16; ++kt) {
      const int s = kt % K1_STAGES;
      const uint32_t ph = (kt / K1_STAGES) & 1;
      mbar_wait(bar_full + 8 * s, ph);
      const uint32_t sa = sbase + s * K1_STAGE_BYTES + cw * 16384;
      const uint32_t sb = sbase + s * K1_STAGE_BYTES + K1_A_BYTES;
      wgmma_fence();
#pragma unroll
      for (int kk = 0; kk < 4; ++kk) {
        const uint64_t db = make_desc(sb + kk * 2048, 8192, 1024, 1);
        wgmma_n192_ss_tb(acc[0], make_desc(sa + kk * 32, 16, 1024, 1), db, 1);
        wgmma_n192_ss_tb(acc[1], make_desc(sa + 8192 + kk * 32, 16, 1024, 1), db, 1);
      }
      wgmma_commit();
      if (kt > 0) {
        wgmma_wait<1>();
        if (lt == 0) mbar_arrive(bar_empty + 8 * ((kt - 1) % K1_STAGES));
      }
    }
    wgmma_wait<0>();
    TSTAMPW(0, 1, tid == 128);
    named_bar(1, 256);
    TSTAMPW(0, 2, tid == 128);

#pragma unroll
    for (int mi = 0; mi < 2; ++mi) {
      const uint32_t rbase = sbase + (uint32_t)(cw * 128 + mi * 64 + warp * 16 + g) * 128u + (uint32_t)c * 4u;
#pragma unroll
      for (int j = 0; j < 8; ++j) {
        const uint32_t off = rbase + (uint32_t)((j ^ g) * 16);
        sts32(off + E_PK, phi2(acc[mi][32 + 4 * j], acc[mi][32 + 4 * j + 1]));
        sts32(off + E_PK + 1024, phi2(acc[mi][32 + 4 * j + 2], acc[mi][32 + 4 * j + 3]));
        sts32(off + E_V, pack_bf16(acc[mi][64 + 4 * j], acc[mi][64 + 4 * j + 1]));
        sts32(off + E_V + 1024, pack_bf16(acc[mi][64 + 4 * j + 2], acc[mi][64 + 4 * j + 3]));
      }
    }
    {
      const int t2 = tid - 128;
      if (t2 < 128) *reinterpret_cast<uint32_t*>(sptr + E_ONES + t2 * 4) = 0x3F803F80u;
      for (int i = t2; i < 9216 / 16; i += 256) *reinterpret_cast<uint4*>(sptr + E_KVB + i * 16) = make_uint4(0, 0, 0, 0);
    }
    fence_proxy_async();
    TSTAMPW(0, 3, tid == 128);
    named_bar(1, 256);
    float kvacc[32], zacc[4];
#pragma unroll
    for (int i = 0; i < 32; ++i) kvacc[i] = 0.f;
#pragma unroll
    for (int i = 0; i < 4; ++i) zacc[i] = 0.f;
    wgmma_fence();
#pragma unroll
    for (int kk = 0; kk < 8; ++kk) {
      const uint64_t da = make_desc(sbase + E_PK + cw * 16384 + kk * 2048, 8192, 1024, 1);
      const uint64_t db = make_desc(sbase + E_V + cw * 16384 + kk * 2048, 8192, 1024, 1);
      wgmma_n64_ss_tatb(kvacc, da, db, 1);
      wgmma_n8_ss_ta(zacc, da, make_desc(sbase + E_ONES, 128, 128, 0), 1);
    }
    wgmma_commit();
    wgmma_wait<0>();
    TSTAMPW(0, 4, tid == 128);
    float* xch = reinterpret_cast<float*>(sptr + E_XCH);
    const int d0 = warp * 16 + g;
    float sel[16];
#pragma unroll
    for (int i = 0; i < 16; ++i) sel[i] = (warp < 2) ? kvacc[i] : kvacc[16 + i];
    if (cw == 1) {
#pragma unroll
      for (int j = 0; j < 4; ++j) {
        *reinterpret_cast<float2*>(&xch[d0 * 36 + j * 8 + 2 * c]) = make_float2(sel[4 * j], sel[4 * j + 1]);
        *reinterpret_cast<float2*>(&xch[(d0 + 8) * 36 + j * 8 + 2 * c]) = make_float2(sel[4 * j + 2], sel[4 * j + 3]);
      }
      if (c == 0) { xch[d0 * 36 + 32] = zacc[0]; xch[(d0 + 8) * 36 + 32] = zacc[2]; }
    }
    named_bar(1, 256);
    float* gp = g_part + (size_t)(hp * 8 + mb) * (64 * 36);
    if (cw == 0) {
#pragma unroll
      for (int j = 0; j < 4; ++j) {
        float2 o0 = *reinterpret_cast<float2*>(&xch[d0 * 36 + j * 8 + 2 * c]);
        float2 o1 = *reinterpret_cast<float2*>(&xch[(d0 + 8) * 36 + j * 8 + 2 * c]);
        __stcg(reinterpret_cast<float2*>(&gp[d0 * 36 + j * 8 + 2 * c]), make_float2(sel[4 * j] + o0.x, sel[4 * j + 1] + o0.y));
        __stcg(reinterpret_cast<float2*>(&gp[(d0 + 8) * 36 + j * 8 + 2 * c]), make_float2(sel[4 * j + 2] + o1.x, sel[4 * j + 3] + o1.y));
      }
      if (c == 0) {
        __stcg(&gp[d0 * 36 + 32], zacc[0] + xch[d0 * 36 + 32]);
        __stcg(&gp[(d0 + 8) * 36 + 32], zacc[2] + xch[(d0 + 8) * 36 + 32]);
      }
      named_bar(2, 128);
      if (lt == 0) {
        asm volatile("fence.acq_rel.gpu;" ::: "memory");
        asm volatile("red.relaxed.gpu.global.add.u32 [%0], %1;" ::"l"(&g_cnt[hp]), "r"(1u) : "memory");
      }
    }
    TSTAMPW(0, 5, tid == 128);
    uint32_t pqf[2][16];
#pragma unroll
    for (int mi = 0; mi < 2; ++mi) {
#pragma unroll
      for (int j = 0; j < 8; ++j) {
        pqf[mi][2 * j]     = phi2(acc[mi][4 * j], acc[mi][4 * j + 1]);
        pqf[mi][2 * j + 1] = phi2(acc[mi][4 * j + 2], acc[mi][4 * j + 3]);
      }
    }
    if (tid == 128) {
      unsigned int v = 0;
      for (int it = 0; it < (1 << 22); ++it) {
        asm volatile("ld.acquire.gpu.global.u32 %0, [%1];" : "=r"(v) : "l"(&g_cnt[hp]) : "memory");
        if (v >= 8u) break;
      }
    }
    named_bar(1, 256);
    TSTAMPW(0, 6, tid == 128);
    {
      const int t2 = tid - 128;
      const float* pb = g_part + (size_t)hp * 8 * (64 * 36);
      float4 sm4[3];
#pragma unroll
      for (int i = 0; i < 3; ++i) {
        const int idx = min(t2 + 256 * i, 575);
        float4 v[8];
#pragma unroll
        for (int m = 0; m < 8; ++m) v[m] = __ldcg(reinterpret_cast<const float4*>(&pb[m * (64 * 36) + idx * 4]));
        sm4[i] = v[0];
#pragma unroll
        for (int m = 1; m < 8; ++m) { sm4[i].x += v[m].x; sm4[i].y += v[m].y; sm4[i].z += v[m].z; sm4[i].w += v[m].w; }
      }
#pragma unroll
      for (int i = 0; i < 3; ++i) {
        const int idx = t2 + 256 * i;
        if (idx < 576) {
          const int k = idx / 9, e4 = idx - k * 9;
          const uint32_t kofs = (uint32_t)((k & 7) * 2);
          if (e4 < 8) {
            const int n = (k >> 5) * 32 + e4 * 4;
            const float vals[4] = {sm4[i].x, sm4[i].y, sm4[i].z, sm4[i].w};
#pragma unroll
            for (int q = 0; q < 4; ++q)
              *reinterpret_cast<__nv_bfloat16*>(sptr + E_KVB + (n + q) * 128 + (((k >> 3) ^ ((n + q) & 7)) * 16) + kofs) =
                  __float2bfloat16_rn(vals[q]);
          } else {
            const int n = 64 + (k >> 5);
            *reinterpret_cast<__nv_bfloat16*>(sptr + E_KVB + n * 128 + (((k >> 3) ^ (n & 7)) * 16) + kofs) =
                __float2bfloat16_rn(sm4[i].x);
          }
        }
      }
    }
    fence_proxy_async();
    named_bar(1, 256);
    TSTAMPW(0, 7, tid == 128);
    float nacc[2][36];
#pragma unroll
    for (int i = 0; i < 36; ++i) { nacc[0][i] = 0.f; nacc[1][i] = 0.f; }
    wgmma_fence();
#pragma unroll
    for (int mi = 0; mi < 2; ++mi)
#pragma unroll
      for (int ks = 0; ks < 4; ++ks)
        wgmma_n72_rs(nacc[mi], pqf[mi][4 * ks], pqf[mi][4 * ks + 1], pqf[mi][4 * ks + 2], pqf[mi][4 * ks + 3],
                     make_desc(sbase + E_KVB + ks * 32, 16, 1024, 1), 1);
    wgmma_commit();
    wgmma_wait<0>();
#pragma unroll
    for (int mi = 0; mi < 2; ++mi) {
      const int src = lane & ~3;
      const float dn00 = __shfl_sync(0xffffffffu, nacc[mi][32], src);
      const float dn01 = __shfl_sync(0xffffffffu, nacc[mi][33], src);
      const float dn10 = __shfl_sync(0xffffffffu, nacc[mi][34], src);
      const float dn11 = __shfl_sync(0xffffffffu, nacc[mi][35], src);
      const uint32_t dp0 = pack_bf16(dn00, dn01), dp1 = pack_bf16(dn10, dn11);
      const uint32_t dq0 = pack_bf16(lo_f(dp0) + 1e-6f, hi_f(dp0) + 1e-6f), dq1 = pack_bf16(lo_f(dp1) + 1e-6f, hi_f(dp1) + 1e-6f);
      const float r00 = __frcp_rn(lo_f(dq0)), r01 = __frcp_rn(hi_f(dq0));
      const float r10 = __frcp_rn(lo_f(dq1)), r11 = __frcp_rn(hi_f(dq1));
      const uint32_t rbase = sbase + E_O + (uint32_t)(cw * 128 + mi * 64 + warp * 16 + g) * 128u + (uint32_t)c * 4u;
#pragma unroll
      for (int j = 0; j < 8; ++j) {
        const float ra = j < 4 ? r00 : r01, rb = j < 4 ? r10 : r11;
        const uint32_t off = rbase + (uint32_t)((j ^ g) * 16);
        const uint32_t p0 = pack_bf16(nacc[mi][4 * j], nacc[mi][4 * j + 1]), p1 = pack_bf16(nacc[mi][4 * j + 2], nacc[mi][4 * j + 3]);
        sts32(off, pack_bf16(lo_f(p0) * ra, hi_f(p0) * ra));
        sts32(off + 1024, pack_bf16(lo_f(p1) * rb, hi_f(p1) * rb));
      }
    }
    fence_proxy_async();
    named_bar(2 + cw, 128);
    TSTAMPW(0, 8, tid == 128);
    if (lt == 0) {
      tma_store_2d(&tm_o, sbase + E_O + cw * 16384, hp * 64, mb * 256 + cw * 128);
      bulk_commit();
      bulk_wait0_read();
    }
    TSTAMPW(0, 9, tid == 128);
    GSTAMP(0, 15, tid == 128);
  }
}

constexpr int K3_STAGES = 5;
constexpr int K3_STAGE_BYTES = 32768;
constexpr int K3_OFF_B = K3_STAGES * K3_STAGE_BYTES;
constexpr int K3_OFF_BAR = K3_OFF_B + 32768;
constexpr int K3_SMEM = K3_OFF_BAR + 1024 + 128;

__global__ void __launch_bounds__(384, 1)
k3_out(const __grid_constant__ CUtensorMap tm_o, const __grid_constant__ CUtensorMap tm_wo,
       const __grid_constant__ CUtensorMap tm_b, const __grid_constant__ CUtensorMap tm_out) {
  extern __shared__ uint8_t smem_raw[];
  const uint32_t sbase = (smem_u32(smem_raw) + 1023u) & ~1023u;
  const uint32_t bar_full = sbase + K3_OFF_BAR;
  const uint32_t bar_empty = bar_full + 8 * K3_STAGES;
  const uint32_t bar_b = bar_empty + 8 * K3_STAGES;
  const int tid = threadIdx.x;
  const int wg = tid >> 7;
  const int nb = blockIdx.x & 7;
  const int mb = blockIdx.x >> 3;
  if (tid == 0) {
    asm volatile("prefetch.tensormap [%0];" ::"l"(&tm_o) : "memory");
    asm volatile("prefetch.tensormap [%0];" ::"l"(&tm_wo) : "memory");
    asm volatile("prefetch.tensormap [%0];" ::"l"(&tm_b) : "memory");
    asm volatile("prefetch.tensormap [%0];" ::"l"(&tm_out) : "memory");
    for (int s = 0; s < K3_STAGES; ++s) {
      mbar_init(bar_full + 8 * s, 1);
      mbar_init(bar_empty + 8 * s, 2);
    }
    mbar_init(bar_b, 1);
    asm volatile("fence.mbarrier_init.release.cluster;" ::: "memory");
  }
  __syncthreads();
  asm volatile("griddepcontrol.wait;" ::: "memory");
  if (tid == 0 && blockIdx.x < 16) g_cnt[blockIdx.x] = 0;
  TSTAMPW(2, 0, tid == 128);
  GSTAMP(2, 14, tid == 128);
  if (wg == 0) {
    reg_dealloc<24>();
    if (tid == 0) {
      for (int kt = 0; kt < 16; ++kt) {
        const int s = kt % K3_STAGES;
        const uint32_t ph = (kt / K3_STAGES) & 1;
        mbar_wait(bar_empty + 8 * s, ph ^ 1);
        mbar_expect_tx(bar_full + 8 * s, K3_STAGE_BYTES);
        const uint32_t sa = sbase + s * K3_STAGE_BYTES;
        tma_load_2d(sa, &tm_o, bar_full + 8 * s, kt * 64, mb * 128);
        tma_load_2d(sa + 16384, &tm_wo, bar_full + 8 * s, nb * 128, kt * 64);
        tma_load_2d(sa + 24576, &tm_wo, bar_full + 8 * s, nb * 128 + 64, kt * 64);
        if (kt == 3) {
          mbar_expect_tx(bar_b, 32768);
#pragma unroll
          for (int q = 0; q < 2; ++q)
            tma_load_2d(sbase + K3_OFF_B + q * 16384, &tm_b, bar_b, mb * 128 + q * 64, nb * 128);
        }
      }
    }
  } else {
    reg_alloc<240>();
    const int cw = wg - 1;
    const int lt = tid & 127;
    const int warp = lt >> 5, lane = lt & 31, g = lane >> 2, c = lane & 3;
    float acc[64];
#pragma unroll
    for (int i = 0; i < 64; ++i) acc[i] = 0.f;
    for (int kt = 0; kt < 16; ++kt) {
      const int s = kt % K3_STAGES;
      const uint32_t ph = (kt / K3_STAGES) & 1;
      mbar_wait(bar_full + 8 * s, ph);
      const uint32_t sa = sbase + s * K3_STAGE_BYTES + cw * 8192;
      const uint32_t sb = sbase + s * K3_STAGE_BYTES + 16384;
      wgmma_fence();
#pragma unroll
      for (int kk = 0; kk < 4; ++kk)
        wgmma_n128_ss_tb(acc, make_desc(sa + kk * 32, 16, 1024, 1), make_desc(sb + kk * 2048, 8192, 1024, 1), 1);
      wgmma_commit();
      if (kt > 0) {
        wgmma_wait<1>();
        if (lt == 0) mbar_arrive(bar_empty + 8 * ((kt - 1) % K3_STAGES));
      }
    }
    wgmma_wait<0>();
    TSTAMPW(2, 1, tid == 128);
    const int r0 = mb * 128 + cw * 64 + warp * 16 + g;
    const float g0 = g_gate[r0], g1 = g_gate[r0 + 8];
    const __nv_bfloat162 gg0 = __float2bfloat162_rn(g0), gg1 = __float2bfloat162_rn(g1);
    const __nv_bfloat162 hh0 = __float2bfloat162_rn(1.f - g0), hh1 = __float2bfloat162_rn(1.f - g1);
    mbar_wait(bar_b, 0);
    named_bar(3, 256);
    const uint32_t obase = sbase + (uint32_t)(cw * 64 + warp * 16 + g) * 128u + (uint32_t)c * 4u;
    const int lm = lane >> 3;
#pragma unroll
    for (int j2 = 0; j2 < 8; ++j2) {
      const int dd = 16 * j2 + 8 * (lm >> 1) + (lane & 7);
      uint32_t b0, b1, b2, b3;
      ldsm_x4_t(sbase + K3_OFF_B + cw * 16384 + (uint32_t)dd * 128u + (uint32_t)(((2 * warp + (lm & 1)) ^ (dd & 7)) * 16), b0, b1, b2, b3);
#pragma unroll
      for (int jj = 0; jj < 2; ++jj) {
        const int j = 2 * j2 + jj;
        uint32_t bb0 = jj ? b2 : b0, bb1 = jj ? b3 : b1;
        const uint32_t off = obase + (uint32_t)(j >> 3) * 16384u + (uint32_t)(((j & 7) ^ g) * 16);
        uint32_t a0 = pack_bf16(acc[4 * j], acc[4 * j + 1]), a1 = pack_bf16(acc[4 * j + 2], acc[4 * j + 3]);
        __nv_bfloat162 x0 = __hadd2(__hmul2(gg0, *reinterpret_cast<__nv_bfloat162*>(&a0)), __hmul2(hh0, *reinterpret_cast<__nv_bfloat162*>(&bb0)));
        __nv_bfloat162 x1 = __hadd2(__hmul2(gg1, *reinterpret_cast<__nv_bfloat162*>(&a1)), __hmul2(hh1, *reinterpret_cast<__nv_bfloat162*>(&bb1)));
        sts32(off, *reinterpret_cast<uint32_t*>(&x0));
        sts32(off + 1024, *reinterpret_cast<uint32_t*>(&x1));
      }
    }
    fence_proxy_async();
    named_bar(1 + cw, 128);
    if (lt == 0) {
      tma_store_2d(&tm_out, sbase + cw * 8192, nb * 128, mb * 128 + cw * 64);
      tma_store_2d(&tm_out, sbase + 16384 + cw * 8192, nb * 128 + 64, mb * 128 + cw * 64);
      bulk_commit();
      bulk_wait0_read();
    }
    TSTAMPW(2, 2, tid == 128);
    GSTAMP(2, 15, tid == 128);
  }
}

constexpr int KS_UP = 72;
constexpr int KW_U = 0;
constexpr int KW_TAPS = 5760;
constexpr int KW_Y = KW_TAPS + 7104;
constexpr int KW_W = KW_Y + 9216;
constexpr int KW_KD = KW_W + 3072;
constexpr int KW_SIZE = KW_W + 6144;
constexpr int KS_SMEM = 8 * KW_SIZE;
constexpr int TQ_NEAR = 0, TQ_T23 = 536;

__device__ __forceinline__ uint2 lds64(uint32_t addr) {
  uint2 v;
  asm volatile("ld.shared.v2.b32 {%0,%1}, [%2];" : "=r"(v.x), "=r"(v.y) : "r"(addr));
  return v;
}
template <int D, int JLO, int JHI, int KLO, int KHI>
__device__ __forceinline__ void tier_class(float (&acc)[8][4], uint32_t arr_addr, uint32_t zero_addr, uint32_t qa, int lane, int hf) {
  constexpr int NQ = JHI - JLO + 1;
  uint2 Q[NQ];
#pragma unroll
  for (int i = 0; i < NQ; ++i) Q[i] = lds64(qa + (uint32_t)((JLO + i) * 64));
  const int mi = lane >> 3;
  const int brow = (mi >> 1) * 8 + (lane & 7);
#pragma unroll
  for (int k = KLO; k <= KHI; ++k) {
    if (D == 8 && 2 * hf + 1 - k < 0) continue;
#pragma unroll
    for (int ks = 0; ks < 4; ++ks) {
      uint32_t addr;
      if (D == 8) {
        const int ip = 2 * hf + (mi & 1) - k;
        addr = (ip < 0) ? zero_addr : arr_addr + (uint32_t)(64 * ip + 16 * ks + brow) * 16u;
      } else {
        addr = arr_addr + (uint32_t)(16 * ks + brow) * 32u + (uint32_t)(mi & 1) * 16u;
      }
      bool any = false;
#pragma unroll
      for (int nt = 0; nt < 8; ++nt) {
        const int j = 8 * k + nt - 2 * ks;
        if (j >= JLO && j <= JHI) any = true;
      }
      if (!any) continue;
      uint32_t a0, a1, a2, a3;
      ldsm_x4_t(addr, a0, a1, a2, a3);
#pragma unroll
      for (int nt = 0; nt < 8; ++nt) {
        const int j = 8 * k + nt - 2 * ks;
        if (j < JLO || j > JHI) continue;
        if (D == 16) {
          if ((nt >> 2) == hf) mma_bf16(acc[nt], a0, a1, a2, a3, Q[j - JLO].x, Q[j - JLO].y);
        } else {
          mma_bf16(acc[nt], a0, a1, a2, a3, Q[j - JLO].x, Q[j - JLO].y);
        }
      }
    }
  }
}

__global__ void __launch_bounds__(512, 1)
ks_s4d(const __nv_bfloat16* __restrict__ x, const __nv_bfloat16* __restrict__ lar, const __nv_bfloat16* __restrict__ aim,
       const __nv_bfloat16* __restrict__ cre, const __nv_bfloat16* __restrict__ cim,
       const __nv_bfloat16* __restrict__ logdt, const __nv_bfloat16* __restrict__ dskip) {
  extern __shared__ __align__(128) uint8_t sm[];
  const int tid = threadIdx.x, warp = tid >> 5, lane = tid & 31, g = lane >> 2, c = lane & 3;
  const int ch = warp >> 1, hf = warp & 1;
  const int l64 = hf * 32 + lane;
  const int d0 = blockIdx.x * 8;
  const int d = d0 + ch;
  uint8_t* wb = sm + ch * KW_SIZE;
  const uint32_t wa = smem_u32(wb);
#define PAIR_SYNC() named_bar(1 + ch, 64)
  asm volatile("griddepcontrol.launch_dependents;");
  TSTAMPW(1, 0, tid == 0);
  GSTAMP(1, 14, tid == 0);
  float* kd = reinterpret_cast<float*>(wb + KW_KD);
  {
    const uint2 vcr = __ldg(reinterpret_cast<const uint2*>(cre + (size_t)d * NST + lane * 4));
    const uint2 vci = __ldg(reinterpret_cast<const uint2*>(cim + (size_t)d * NST + lane * 4));
    float par[2][4];
#pragma unroll
    for (int qq = 0; qq < 2; ++qq) {
      const int m = d * NST + (hf * 2 + qq) * 32 + lane;
      par[qq][0] = __bfloat162float(lar[m]); par[qq][1] = __bfloat162float(aim[m]);
      par[qq][2] = __bfloat162float(cre[m]); par[qq][3] = __bfloat162float(cim[m]);
    }
    const float dt = bf16r(expf(__bfloat162float(logdt[d])));
    float cmax = fmaxf(fmaxf(fmaxf(fabsf(lo_f(vcr.x)), fabsf(hi_f(vcr.x))), fmaxf(fabsf(lo_f(vcr.y)), fabsf(hi_f(vcr.y)))),
                       fmaxf(fmaxf(fabsf(lo_f(vci.x)), fabsf(hi_f(vci.x))), fmaxf(fabsf(lo_f(vci.y)), fabsf(hi_f(vci.y)))));
#pragma unroll
    for (int o = 16; o; o >>= 1) cmax = fmaxf(cmax, __shfl_xor_sync(0xffffffffu, cmax, o));
    if (!(cmax > 0.f)) cmax = 1.f;
    const float cinv = 1.f / cmax;
    const float kscale = 2.f * dt * cmax;
#pragma unroll
    for (int qq = 0; qq < 2; ++qq) {
      par[qq][0] = -bf16r(expf(par[qq][0])) * dt * 1.4426950408889634f;
      par[qq][1] = par[qq][1] * dt * 0.15915494309189535f;
      par[qq][2] *= cinv; par[qq][3] *= cinv;
    }
    TSTAMPW(1, 8, tid == 0 && par[0][0] != 12345.f);
    uint4 xv[2][2];
#pragma unroll
    for (int i = 0; i < 2; ++i) {
      const int t = 2 * tid + 1024 * i;
      xv[i][0] = __ldg(reinterpret_cast<const uint4*>(x + (size_t)t * DM + d0));
      xv[i][1] = __ldg(reinterpret_cast<const uint4*>(x + (size_t)(t + 1) * DM + d0));
    }
    float ka[5][4];
#pragma unroll
    for (int a = 0; a < 5; ++a)
#pragma unroll
      for (int b = 0; b < 4; ++b) ka[a][b] = 0.f;
    float klast = 0.f;
    kgen_half(wa + KW_TAPS + 2624 + hf * 8208, lane, par, ka, klast);
    TSTAMPW(1, 9, tid == 0 && ka[0][0] != 12345.f);
#pragma unroll
    for (int o = 16; o; o >>= 1) klast += __shfl_xor_sync(0xffffffffu, klast, o);
    float* px = reinterpret_cast<float*>(wb + KW_TAPS);
    if (hf == 1) {
#pragma unroll
      for (int a = 0; a < 5; ++a)
#pragma unroll
        for (int e = 0; e < 4; ++e) px[(a * 4 + e) * 32 + lane] = ka[a][e];
      if (lane == 0) px[640] = klast;
    }
    PAIR_SYNC();
    if (hf == 0) {
#pragma unroll
      for (int e = 0; e < 4; ++e) {
        const int pl = g + (e >> 1) * 8, col = 2 * c + (e & 1);
        kd[8 * pl + col] = (ka[0][e] + px[(0 + e) * 32 + lane]) * kscale;
        kd[128 + 8 * pl + col] = (ka[1][e] + px[(4 + e) * 32 + lane]) * kscale;
        kd[256 + 64 * (col >> 2) + 4 * pl + (col & 3)] = (ka[2][e] + px[(8 + e) * 32 + lane]) * kscale;
        kd[384 + 32 * (col >> 1) + 2 * pl + (col & 1)] = (ka[3][e] + px[(12 + e) * 32 + lane]) * kscale;
        kd[512 + 16 * col + pl] = (ka[4][e] + px[(16 + e) * 32 + lane]) * kscale;
      }
      if (lane == 0) kd[640] = (klast + px[640]) * kscale;
    }
    TSTAMPW(1, 10, tid == 0);
    for (int i = tid; i < 8 * 72; i += 512) {
      const int cc = i / 72, r = i % 72;
      *reinterpret_cast<uint4*>(sm + cc * KW_SIZE + KW_U + r * 16) = make_uint4(0, 0, 0, 0);
    }
#pragma unroll
    for (int i = 0; i < 2; ++i) {
      const int t = 2 * tid + 1024 * i;
      const uint32_t off = (uint32_t)(((8 + (t >> 6)) * KS_UP + (t & 63)) * 2);
      const uint32_t w0[4] = {xv[i][0].x, xv[i][0].y, xv[i][0].z, xv[i][0].w};
      const uint32_t w1[4] = {xv[i][1].x, xv[i][1].y, xv[i][1].z, xv[i][1].w};
#pragma unroll
      for (int q = 0; q < 4; ++q) {
        *reinterpret_cast<uint32_t*>(sm + (2 * q) * KW_SIZE + KW_U + off) = __byte_perm(w0[q], w1[q], 0x5410);
        *reinterpret_cast<uint32_t*>(sm + (2 * q + 1) * KW_SIZE + KW_U + off) = __byte_perm(w0[q], w1[q], 0x7632);
      }
    }
  }
  __syncthreads();
  TSTAMPW(1, 2, tid == 0);
  const uint32_t ta = wa + KW_TAPS;
  {
    auto knear = [&](int j) -> float {
      const int jc = min(max(j, 0), 510);
      const int idx = jc <= 256 ? jc : 128 + ((jc + 1) >> 2) * 2 + ((jc & 3) == 2 ? 1 : 0);
      float v = kd[idx];
      v = (jc == j) ? v : 0.f;
      return (j == 510) ? v - kd[384] : v;
    };
#pragma unroll
    for (int it = 0; it < 9; ++it) {
      const int xx = l64 - 16 + 64 * it;
      const float v1 = knear(xx);
      float v0 = __shfl_up_sync(0xffffffffu, v1, 1);
      if (lane == 0) v0 = knear(xx - 1);
      const uint32_t w = pack_bf16(v1, v0);
      if (xx >= -8 && xx < 528) sts32(ta + (uint32_t)(TQ_NEAR + xx + 8) * 8, w);
      if (xx + 8 < 528) sts32(ta + (uint32_t)(TQ_NEAR + xx + 16) * 8 + 4, w);
    }
#pragma unroll
    for (int q = 0; q < 4; ++q) {
      const int base = q < 2 ? 256 + q : 384 + (q - 2);
#pragma unroll
      for (int it = 0; it < 2; ++it) {
        const int xx = 48 + l64 + 64 * it;
        if (xx < 144) {
          const float v1 = (xx >= 64 && xx < 128) ? kd[base + 2 * xx] : 0.f;
          const float v0 = (xx >= 65 && xx < 129) ? kd[base + 2 * (xx - 1)] : 0.f;
          const uint32_t w = pack_bf16(v1, v0);
          if (xx >= 56) sts32(ta + (uint32_t)(TQ_T23 + q * 88 + xx - 56) * 8, w);
          if (xx + 8 < 144) sts32(ta + (uint32_t)(TQ_T23 + q * 88 + xx + 8 - 56) * 8 + 4, w);
        }
      }
    }
  }
  const uint32_t ua = wa + KW_U, w0a = wa + KW_W, w1a = wa + KW_W + 3072, ya = wa + KW_Y;
  auto uchunk = [&](int x8) -> uint4 {
    return lds128(ua + (uint32_t)(((8 + (x8 >> 6)) * KS_UP + (x8 & 63)) * 2));
  };
  float* ys = reinterpret_cast<float*>(wb + KW_Y);
#define YIDX(t) ((((t) >> 6) * 72) + ((t) & 63))
  {
    const float k1024 = kd[512];
    const float kk2 = kd[256 + 2 * (64 + l64)];
    const float kk3a = kd[384 + 2 * (64 + l64)], kk3b = kd[640];
    for (int q = l64; q < 255; q += 64) sts128(ya + (uint32_t)YIDX(4 * q) * 4, 0u, 0u, 0u, 0u);
    for (int x0 = 8 * l64; x0 < 1032; x0 += 512) {
      const uint4 va = uchunk(x0 - 8), vb = uchunk(x0);
      const float f[9] = {hi_f(va.w), lo_f(vb.x), hi_f(vb.x), lo_f(vb.y), hi_f(vb.y), lo_f(vb.z), hi_f(vb.z), lo_f(vb.w), hi_f(vb.w)};
      float o[8];
#pragma unroll
      for (int e = 0; e < 8; ++e) o[e] = -k1024 * (f[e] + f[e + 1]);
      const int t = 1020 + x0;
      sts128(ya + (uint32_t)YIDX(t) * 4, __float_as_uint(o[0]), __float_as_uint(o[1]), __float_as_uint(o[2]), __float_as_uint(o[3]));
      if (t + 4 < 2048)
        sts128(ya + (uint32_t)YIDX(t + 4) * 4, __float_as_uint(o[4]), __float_as_uint(o[5]), __float_as_uint(o[6]), __float_as_uint(o[7]));
    }
    PAIR_SYNC();
    const uint4 u04 = uchunk(0);
    const float u0 = lo_f(u04.x), u1 = hi_f(u04.x), u2 = lo_f(u04.y), u3 = hi_f(u04.y);
    const float s1 = u0 + u1, s2 = s1 + u2, s3 = s2 + u3;
    {
      const int m = 64 + l64;
      ys[YIDX(8 * m - 2)] += kk2 * u0;
      ys[YIDX(8 * m - 1)] += kk2 * s1;
    }
    PAIR_SYNC();
    {
      const int m = 64 + l64;
      float4* p = reinterpret_cast<float4*>(&ys[YIDX(16 * m - 4)]);
      float4 v = *p;
      v.x += kk3a * u0; v.y += kk3a * s1; v.z += kk3a * s2; v.w += kk3a * s3;
      *p = v;
      if (l64 == 0) {
        float4* p2 = reinterpret_cast<float4*>(&ys[YIDX(2044)]);
        float4 v2 = *p2;
        v2.x += kk3b * u0; v2.y += kk3b * s1; v2.z += kk3b * s2; v2.w += kk3b * s3;
        *p2 = v2;
      }
    }
  }
  TSTAMPW(1, 3, tid == 0);

  const int e0 = g - 2 * c;
  const uint32_t q_t23 = ta + (uint32_t)(TQ_T23 + e0 - 56) * 8;
  float acc[8][4];
  auto zero_acc = [&]() {
#pragma unroll
    for (int b = 0; b < 8; ++b)
#pragma unroll
      for (int e = 0; e < 4; ++e) acc[b][e] = 0.f;
  };
#define KS_PREFIX(x0)                                                             \
  float pre[24];                                                                  \
  {                                                                               \
    const uint4 va = uchunk((x0) - 8), vb = uchunk(x0), vc = uchunk((x0) + 8);    \
    const uint32_t ww[12] = {va.x, va.y, va.z, va.w, vb.x, vb.y, vb.z, vb.w, vc.x, vc.y, vc.z, vc.w}; \
    float run = 0.f;                                                              \
    _Pragma("unroll") for (int i = 0; i < 12; ++i) {                              \
      run += lo_f(ww[i]); pre[2 * i] = run;                                       \
      run += hi_f(ww[i]); pre[2 * i + 1] = run;                                   \
    }                                                                             \
  }
#define KS_WIN(o, lo, hi) (pre[8 + (o) + (hi)] - pre[8 + (o) + (lo) - 1])
#define KS_WIN8(lo, hi) pack_bf16(KS_WIN(0, lo, hi), KS_WIN(1, lo, hi)), pack_bf16(KS_WIN(2, lo, hi), KS_WIN(3, lo, hi)), \
                        pack_bf16(KS_WIN(4, lo, hi), KS_WIN(5, lo, hi)), pack_bf16(KS_WIN(6, lo, hi), KS_WIN(7, lo, hi))

  float nacc[8][4];
#pragma unroll
  for (int b = 0; b < 8; ++b)
#pragma unroll
    for (int e = 0; e < 4; ++e) nacc[b][e] = 0.f;
  auto near_tier = [&]() {
  {
    const uint32_t qn = ta + (uint32_t)(TQ_NEAR + e0 + 8) * 8;
#pragma unroll
    for (int k = 0; k < 9; ++k) {
      uint2 Q[14];
#pragma unroll
      for (int i = 0; i < 14; ++i) {
        const int j = 8 * k - 6 + i;
        if (j >= 0 && j <= 65) Q[i] = lds64(qn + (uint32_t)(j * 64)); else Q[i] = make_uint2(0u, 0u);
      }
#pragma unroll
      for (int ks = 0; ks < 4; ++ks) {
        uint32_t a0, a1, a2, a3;
        ldsm_x4(ua + (uint32_t)(((16 * hf + (lane & 15) - k + 8) * KS_UP + ks * 16 + (lane >> 4) * 8) * 2), a0, a1, a2, a3);
#pragma unroll
        for (int nt = 0; nt < 8; ++nt) {
          const int j = 8 * k + nt - 2 * ks;
          if (j < 0 || j > 65) continue;
          mma_bf16(nacc[nt], a0, a1, a2, a3, Q[j - (8 * k - 6)].x, Q[j - (8 * k - 6)].y);
        }
      }
    }
  }
  };
  if (ch & 1) near_tier();
  PAIR_SYNC();
#pragma unroll
  for (int it = 0; it < 2; ++it) {
    const int x0 = 8 * l64 + 512 * it;
    KS_PREFIX(x0);
    sts128(w0a + x0 * 2, KS_WIN8(-4, 4));
    if (x0 + 8 < 1024) sts128(w1a + (x0 + 8) * 2, KS_WIN8(-3, 3));
  }
  if (l64 == 0) {
    const uint4 u04 = uchunk(0);
    const float u0 = lo_f(u04.x), u1 = hi_f(u04.x), u2 = lo_f(u04.y);
    sts128(w1a, 0u, 0u, pack_bf16(0.f, u0), pack_bf16(u0 + u1, u0 + u1 + u2));
  }
  PAIR_SYNC();
  zero_acc();
  tier_class<16, 8, 17, 1, 1>(acc, w0a, ua, q_t23 + 2 * 88 * 8, lane, hf);
  tier_class<16, 8, 17, 1, 1>(acc, w1a, ua, q_t23 + 3 * 88 * 8, lane, hf);
  {
    float old[4][4];
#pragma unroll
    for (int n4 = 0; n4 < 4; ++n4)
#pragma unroll
      for (int e = 0; e < 4; ++e) old[n4][e] = ys[YIDX(16 * (64 + 8 * (4 * hf + n4) + 2 * c + (e & 1)) + g + 8 * (e >> 1))];
#pragma unroll
    for (int n4 = 0; n4 < 4; ++n4)
#pragma unroll
      for (int e = 0; e < 4; ++e)
        ys[YIDX(16 * (64 + 8 * (4 * hf + n4) + 2 * c + (e & 1)) + g + 8 * (e >> 1))] = old[n4][e] + (hf ? acc[4 + n4][e] : acc[n4][e]);
  }
  PAIR_SYNC();
#pragma unroll
  for (int it = 0; it < 3; ++it) {
    const int x0 = 8 * l64 + 512 * it;
    KS_PREFIX(x0);
    sts128(w0a + x0 * 2, KS_WIN8(-2, 2));
    sts128(w1a + x0 * 2, KS_WIN8(-5, -3));
  }
  PAIR_SYNC();
  zero_acc();
  tier_class<8, 8, 17, 1, 2>(acc, w0a, ua, q_t23, lane, hf);
  tier_class<8, 8, 17, 1, 2>(acc, w1a, ua, q_t23 + 88 * 8, lane, hf);
  {
    float old[8][4];
#pragma unroll
    for (int nt = 0; nt < 8; ++nt)
#pragma unroll
      for (int e = 0; e < 4; ++e) old[nt][e] = ys[YIDX(8 * (64 * (2 * hf + (e >> 1)) + 8 * nt + 2 * c + (e & 1)) + g)];
#pragma unroll
    for (int nt = 0; nt < 8; ++nt)
#pragma unroll
      for (int e = 0; e < 4; ++e)
        ys[YIDX(8 * (64 * (2 * hf + (e >> 1)) + 8 * nt + 2 * c + (e & 1)) + g)] = old[nt][e] + acc[nt][e];
  }
  PAIR_SYNC();
  if (!(ch & 1)) near_tier();
  TSTAMPW(1, 5, tid == 0);
#pragma unroll
  for (int nt = 0; nt < 8; ++nt)
#pragma unroll
    for (int h = 0; h < 2; ++h) {
      const float2 v = *reinterpret_cast<const float2*>(&ys[(16 * hf + g + 8 * h) * 72 + 8 * nt + 2 * c]);
      nacc[nt][2 * h] += v.x; nacc[nt][2 * h + 1] += v.y;
    }
  TSTAMPW(1, 6, tid == 0);
  PAIR_SYNC();
  const float dsk = __bfloat162float(dskip[d]);
#pragma unroll
  for (int nt = 0; nt < 8; ++nt)
#pragma unroll
    for (int h = 0; h < 2; ++h) {
      const uint32_t addr = ua + (uint32_t)(((8 + 16 * hf + g + 8 * h) * KS_UP + 8 * nt + 2 * c) * 2);
      const uint32_t up = lds32(addr);
      const uint32_t yp = pack_bf16(nacc[nt][2 * h], nacc[nt][2 * h + 1]);
      const uint32_t sp = pack_bf16(lo_f(up) * dsk, hi_f(up) * dsk);
      sts32(addr, pack_bf16(lo_f(yp) + lo_f(sp), hi_f(yp) + hi_f(sp)));
    }
  PAIR_SYNC();
#pragma unroll
  for (int i = 0; i < 4; ++i) {
    const int x8 = 8 * (l64 + 64 * i);
    *reinterpret_cast<uint4*>(g_b + (size_t)d * SEQ + x8) = uchunk(x8);
  }
  asm volatile("griddepcontrol.wait;" ::: "memory");
  TSTAMPW(1, 7, tid == 0);
  GSTAMP(1, 15, tid == 0);
}

typedef CUresult (*EncodeFn)(CUtensorMap*, CUtensorMapDataType, cuuint32_t, void*, const cuuint64_t*, const cuuint64_t*,
                             const cuuint32_t*, const cuuint32_t*, CUtensorMapInterleave, CUtensorMapSwizzle,
                             CUtensorMapL2promotion, CUtensorMapFloatOOBfill);

void make_map(EncodeFn fn, CUtensorMap* m, const void* ptr, uint64_t cols, uint64_t rows, uint32_t bc, uint32_t br) {
  cuuint64_t dims[2] = {cols, rows};
  cuuint64_t strides[1] = {cols * 2};
  cuuint32_t box[2] = {bc, br};
  cuuint32_t es[2] = {1, 1};
  fn(m, CU_TENSOR_MAP_DATA_TYPE_BFLOAT16, 2, const_cast<void*>(ptr), dims, strides, box, es,
     CU_TENSOR_MAP_INTERLEAVE_NONE, CU_TENSOR_MAP_SWIZZLE_128B, CU_TENSOR_MAP_L2_PROMOTION_L2_256B,
     CU_TENSOR_MAP_FLOAT_OOB_FILL_NONE);
}

struct HostState {
  bool init = false;
  EncodeFn enc = nullptr;
  void* o_ptr = nullptr;
  void* b_ptr = nullptr;
};
HostState g_hs;

}

extern "C" void kernel_launch(void* const* d_in, const int* in_sizes, int n_in, void* d_out, int out_size) {
  (void)in_sizes; (void)n_in; (void)out_size;
  const __nv_bfloat16* x = (const __nv_bfloat16*)d_in[0];
  const __nv_bfloat16* wqkv = (const __nv_bfloat16*)d_in[1];
  const __nv_bfloat16* wo = (const __nv_bfloat16*)d_in[2];
  const __nv_bfloat16* lar = (const __nv_bfloat16*)d_in[4];
  const __nv_bfloat16* aim = (const __nv_bfloat16*)d_in[5];
  const __nv_bfloat16* cre = (const __nv_bfloat16*)d_in[6];
  const __nv_bfloat16* cim = (const __nv_bfloat16*)d_in[7];
  const __nv_bfloat16* logdt = (const __nv_bfloat16*)d_in[8];
  const __nv_bfloat16* dskip = (const __nv_bfloat16*)d_in[9];
  const __nv_bfloat16* gw = (const __nv_bfloat16*)d_in[10];
  __nv_bfloat16* out = (__nv_bfloat16*)d_out;

  HostState& hs = g_hs;
  if (!hs.init) {
    void* fn = nullptr;
    cudaDriverEntryPointQueryResult qr;
    cudaGetDriverEntryPoint("cuTensorMapEncodeTiled", &fn, cudaEnableDefault, &qr);
    hs.enc = (EncodeFn)fn;
    cudaGetSymbolAddress(&hs.o_ptr, g_o);
    cudaGetSymbolAddress(&hs.b_ptr, g_b);
    cudaFuncSetAttribute(k1_qkv_attn, cudaFuncAttributeMaxDynamicSharedMemorySize, K1_SMEM);
    cudaFuncSetAttribute(k3_out, cudaFuncAttributeMaxDynamicSharedMemorySize, K3_SMEM);
    cudaFuncSetAttribute(ks_s4d, cudaFuncAttributeMaxDynamicSharedMemorySize, KS_SMEM);
    hs.init = true;
  }
  CUtensorMap tm_x, tm_w, tm_o, tm_wo, tm_b, tm_out;
  make_map(hs.enc, &tm_x, x, 1024, 2048, 64, 256);
  make_map(hs.enc, &tm_w, wqkv, 3072, 1024, 64, 64);
  make_map(hs.enc, &tm_o, hs.o_ptr, 1024, 2048, 64, 128);
  make_map(hs.enc, &tm_wo, wo, 1024, 1024, 64, 64);
  make_map(hs.enc, &tm_b, hs.b_ptr, 2048, 1024, 64, 128);
  make_map(hs.enc, &tm_out, out, 1024, 2048, 64, 64);

  cudaStream_t s0 = cudaStreamPerThread;
  k1_qkv_attn<<<128, 384, K1_SMEM, s0>>>(tm_x, tm_w, tm_o, x, lar, aim, cre, cim, wo, gw);
  {
    cudaLaunchAttribute at[1];
    at[0].id = cudaLaunchAttributeProgrammaticStreamSerialization;
    at[0].val.programmaticStreamSerializationAllowed = 1;
    cudaLaunchConfig_t cfg = {};
    cfg.gridDim = dim3(128); cfg.blockDim = dim3(512); cfg.dynamicSmemBytes = KS_SMEM; cfg.stream = s0;
    cfg.attrs = at; cfg.numAttrs = 1;
    cudaLaunchKernelEx(&cfg, ks_s4d, x, lar, aim, cre, cim, logdt, dskip);
    cfg.blockDim = dim3(384); cfg.dynamicSmemBytes = K3_SMEM;
    cudaLaunchKernelEx(&cfg, k3_out, tm_o, tm_wo, tm_b, tm_out);
  }
}
```
